```python
import torch

def _softmax(x, axis=-1):
    return torch.softmax(x, dim=axis)
def _gelu(x):
    return torch.nn.functional.gelu(x, approximate="tanh")
def _silu(x):
    return torch.nn.functional.silu(x)
def _sigmoid(x):
    return torch.sigmoid(x)
def _layernorm(x, axis=-1, eps=1e-5):
    m = x.mean(dim=axis, keepdim=True)
    v = x.var(dim=axis, keepdim=True, unbiased=False)
    return (x - m) / torch.sqrt(v + eps)
def _scatter_add(tgt, idx, src, axis=0):
    return tgt.clone().index_add_(axis, idx, src)
def _segment_sum(src, seg, n):
    out = torch.zeros((n,) + src.shape[1:], dtype=src.dtype)
    return out.index_add_(0, seg, src)
def _pad(x, pw):
    flat = tuple(v for pair in reversed(pw) for v in pair)
    return torch.nn.functional.pad(x, flat)

kernel_name = 'concat_heads__gqa_block_cached__mha_block_cached__near_ridge'

def setup_inputs():

    _w = (lambda a: (lambda t: t.to(torch.bfloat16) if t.is_floating_point() else t)(torch.as_tensor(a)))
    def _A_setup():
        B, Sq, D = 16, 144, 512
        Hq, Hkv, Sk, Dh = 32, 32, 512, 128
        assert Hq % Hkv == 0, (Hq, Hkv)
        return {
            "x": _w((lambda *s: torch.randn(*s, dtype=torch.bfloat16) * 0.8)(B, Sq, D)),
            "k_cache": _w((lambda *s: torch.randn(*s, dtype=torch.bfloat16) * 0.8)(B, Hkv, Sk, Dh)),
            "v_cache": _w((lambda *s: torch.randn(*s, dtype=torch.bfloat16) * 0.05)(B, Hkv, Sk, Dh)),
            "wq": _w((lambda *s: torch.randn(*s, dtype=torch.bfloat16) * 0.8)(D, Hq * Dh) * (D ** -0.5)),
            "wo": _w((lambda *s: torch.randn(*s, dtype=torch.bfloat16) * 0.05)(Hq * Dh, D) * ((Hq * Dh) ** -0.5)),
        }
    _A_in = _A_setup()

    def _B_setup():
        B, Sq, D = 16, 144, 512
        H, Sk, Dh = 32, 512, 128
        return {
            "x": _w((lambda *s: torch.randn(*s, dtype=torch.bfloat16) * 0.8)(B, Sq, D)),
            "k_cache": _w((lambda *s: torch.randn(*s, dtype=torch.bfloat16) * 0.8)(B, H, Sk, Dh)),
            "v_cache": _w((lambda *s: torch.randn(*s, dtype=torch.bfloat16) * 0.05)(B, H, Sk, Dh)),
            "wq": _w((lambda *s: torch.randn(*s, dtype=torch.bfloat16) * 0.8)(D, H * Dh) * (D ** -0.5)),
            "wo": _w((lambda *s: torch.randn(*s, dtype=torch.bfloat16) * 0.05)(H * Dh, D) * ((H * Dh) ** -0.5)),
        }
    _B_in = _B_setup()

    return {
        "A_x": _A_in["x"],
        "A_k_cache": _A_in["k_cache"],
        "A_v_cache": _A_in["v_cache"],
        "A_wq": _A_in["wq"],
        "A_wo": _A_in["wo"],
        "B_x": _B_in["x"],
        "B_k_cache": _B_in["k_cache"],
        "B_v_cache": _B_in["v_cache"],
        "B_wq": _B_in["wq"],
        "B_wo": _B_in["wo"],
    }

def reference(A_x, A_k_cache, A_v_cache, A_wq, A_wo, B_x, B_k_cache, B_v_cache, B_wq, B_wo):
    def _A_ref(x, k_cache, v_cache, wq, wo):
        B, Sq, D = x.shape
        Hq, Dh = 32, 128
        Hkv = k_cache.shape[1]
        rep = Hq // Hkv
        q = (lambda x, *d: x.permute(*d))((x @ wq).reshape(B, Sq, Hq, Dh), 0, 2, 1, 3)
        k = (lambda x, n, axis: torch.repeat_interleave(x, n, dim=axis))(k_cache, rep, axis=1)
        v = (lambda x, n, axis: torch.repeat_interleave(x, n, dim=axis))(v_cache, rep, axis=1)
        scores = torch.einsum("bhqd,bhkd->bhqk", q, k) * (Dh ** -0.5)
        p = _softmax(scores, axis=-1)
        o = torch.einsum("bhqk,bhkd->bhqd", p, v)
        return (lambda x, *d: x.permute(*d))(o, 0, 2, 1, 3).reshape(B, Sq, Hq * Dh) @ wo

    def _B_ref(x, k_cache, v_cache, wq, wo):
        B, Sq, D = x.shape
        H, Dh = 32, 128
        q = (lambda x, *d: x.permute(*d))((x @ wq).reshape(B, Sq, H, Dh), 0, 2, 1, 3)
        scores = torch.einsum("bhqd,bhkd->bhqk", q, k_cache) * (Dh ** -0.5)
        p = _softmax(scores, axis=-1)
        o = torch.einsum("bhqk,bhkd->bhqd", p, v_cache)
        return (lambda x, *d: x.permute(*d))(o, 0, 2, 1, 3).reshape(B, Sq, H * Dh) @ wo

    a = _A_ref(A_x, A_k_cache, A_v_cache, A_wq, A_wo)
    b = _B_ref(B_x, B_k_cache, B_v_cache, B_wq, B_wo)
    return torch.concatenate([a, b], axis=-1)
```

```cpp
#include <cuda_runtime.h>
#include <cuda_bf16.h>
#include <cuda.h>
#include <stdint.h>

constexpr int NB = 16;
constexpr int SQ = 144;
constexpr int DM = 512;
constexpr int NH = 32;
constexpr int SK = 512;
constexpr int DH = 128;
constexpr int HD = NH * DH;
constexpr int N_ITEMS = 2 * NB * NH;

__device__ __nv_bfloat16 g_o[2 * NB * SQ * HD];

__device__ __forceinline__ uint32_t smem_u32(const void* p) {
    return (uint32_t)__cvta_generic_to_shared(p);
}
__device__ __forceinline__ void mbar_init(uint32_t bar, uint32_t count) {
    asm volatile("mbarrier.init.shared::cta.b64 [%0], %1;" :: "r"(bar), "r"(count));
}
__device__ __forceinline__ void mbar_expect_tx(uint32_t bar, uint32_t bytes) {
    asm volatile("mbarrier.arrive.expect_tx.shared::cta.b64 _, [%0], %1;" :: "r"(bar), "r"(bytes) : "memory");
}
__device__ __forceinline__ void mbar_arrive(uint32_t bar) {
    asm volatile("mbarrier.arrive.shared::cta.b64 _, [%0];" :: "r"(bar) : "memory");
}
__device__ __forceinline__ void mbar_wait(uint32_t bar, uint32_t parity) {
    asm volatile(
        "{\n"
        ".reg .pred p;\n"
        "LAB_WAIT:\n"
        "mbarrier.try_wait.parity.shared::cta.b64 p, [%0], %1;\n"
        "@p bra LAB_DONE;\n"
        "bra LAB_WAIT;\n"
        "LAB_DONE:\n"
        "}\n" :: "r"(bar), "r"(parity) : "memory");
}
__device__ __forceinline__ void tma_load_2d(uint32_t dst, const CUtensorMap* map, uint32_t bar, int c0, int c1) {
    asm volatile(
        "cp.async.bulk.tensor.2d.shared::cluster.global.mbarrier::complete_tx::bytes [%0], [%1, {%3, %4}], [%2];"
        :: "r"(dst), "l"(map), "r"(bar), "r"(c0), "r"(c1) : "memory");
}
__device__ __forceinline__ void tma_load_3d(uint32_t dst, const CUtensorMap* map, uint32_t bar, int c0, int c1, int c2) {
    asm volatile(
        "cp.async.bulk.tensor.3d.shared::cluster.global.mbarrier::complete_tx::bytes [%0], [%1, {%3, %4, %5}], [%2];"
        :: "r"(dst), "l"(map), "r"(bar), "r"(c0), "r"(c1), "r"(c2) : "memory");
}
__device__ __forceinline__ void tma_store_3d(const CUtensorMap* map, uint32_t src, int c0, int c1, int c2) {
    asm volatile(
        "cp.async.bulk.tensor.3d.global.shared::cta.bulk_group [%0, {%2, %3, %4}], [%1];"
        :: "l"(map), "r"(src), "r"(c0), "r"(c1), "r"(c2) : "memory");
}
__device__ __forceinline__ void bulk_commit() { asm volatile("cp.async.bulk.commit_group;" ::: "memory"); }
__device__ __forceinline__ void bulk_wait_read0() { asm volatile("cp.async.bulk.wait_group.read 0;" ::: "memory"); }
__device__ __forceinline__ void bulk_wait0() { asm volatile("cp.async.bulk.wait_group 0;" ::: "memory"); }
__device__ __forceinline__ void fence_proxy_async() { asm volatile("fence.proxy.async.shared::cta;" ::: "memory"); }
__device__ __forceinline__ void named_bar_sync(int id, int nthreads) {
    asm volatile("bar.sync %0, %1;" :: "r"(id), "r"(nthreads) : "memory");
}
__device__ __forceinline__ void wgmma_fence() { asm volatile("wgmma.fence.sync.aligned;" ::: "memory"); }
__device__ __forceinline__ void wgmma_commit() { asm volatile("wgmma.commit_group.sync.aligned;" ::: "memory"); }
template <int N> __device__ __forceinline__ void wgmma_wait() {
    asm volatile("wgmma.wait_group.sync.aligned %0;" :: "n"(N) : "memory");
}
template <int R> __device__ __forceinline__ void reg_alloc() { asm volatile("setmaxnreg.inc.sync.aligned.u32 %0;" :: "n"(R)); }
template <int R> __device__ __forceinline__ void reg_dealloc() { asm volatile("setmaxnreg.dec.sync.aligned.u32 %0;" :: "n"(R)); }

__device__ __forceinline__ uint64_t make_desc(uint32_t addr, uint32_t lbo, uint32_t sbo) {
    uint64_t d = 0;
    d |= (uint64_t)((addr & 0x3FFFF) >> 4);
    d |= (uint64_t)((lbo & 0x3FFFF) >> 4) << 16;
    d |= (uint64_t)((sbo & 0x3FFFF) >> 4) << 32;
    d |= (uint64_t)1 << 62;
    return d;
}

#define ACC64(d) \
    "+f"(d[0]), "+f"(d[1]), "+f"(d[2]), "+f"(d[3]), "+f"(d[4]), "+f"(d[5]), "+f"(d[6]), "+f"(d[7]), \
    "+f"(d[8]), "+f"(d[9]), "+f"(d[10]), "+f"(d[11]), "+f"(d[12]), "+f"(d[13]), "+f"(d[14]), "+f"(d[15]), \
    "+f"(d[16]), "+f"(d[17]), "+f"(d[18]), "+f"(d[19]), "+f"(d[20]), "+f"(d[21]), "+f"(d[22]), "+f"(d[23]), \
    "+f"(d[24]), "+f"(d[25]), "+f"(d[26]), "+f"(d[27]), "+f"(d[28]), "+f"(d[29]), "+f"(d[30]), "+f"(d[31]), \
    "+f"(d[32]), "+f"(d[33]), "+f"(d[34]), "+f"(d[35]), "+f"(d[36]), "+f"(d[37]), "+f"(d[38]), "+f"(d[39]), \
    "+f"(d[40]), "+f"(d[41]), "+f"(d[42]), "+f"(d[43]), "+f"(d[44]), "+f"(d[45]), "+f"(d[46]), "+f"(d[47]), \
    "+f"(d[48]), "+f"(d[49]), "+f"(d[50]), "+f"(d[51]), "+f"(d[52]), "+f"(d[53]), "+f"(d[54]), "+f"(d[55]), \
    "+f"(d[56]), "+f"(d[57]), "+f"(d[58]), "+f"(d[59]), "+f"(d[60]), "+f"(d[61]), "+f"(d[62]), "+f"(d[63])

#define REGS64 "{%0, %1, %2, %3, %4, %5, %6, %7, %8, %9, %10, %11, %12, %13, %14, %15, " \
    "%16, %17, %18, %19, %20, %21, %22, %23, %24, %25, %26, %27, %28, %29, %30, %31, " \
    "%32, %33, %34, %35, %36, %37, %38, %39, %40, %41, %42, %43, %44, %45, %46, %47, " \
    "%48, %49, %50, %51, %52, %53, %54, %55, %56, %57, %58, %59, %60, %61, %62, %63}"

template <int TA, int TB>
__device__ __forceinline__ void wgmma_ss_n128(float (&d)[64], uint64_t da, uint64_t db, int scale_d) {
    asm volatile(
        "{\n.reg .pred p;\nsetp.ne.b32 p, %66, 0;\n"
        "wgmma.mma_async.sync.aligned.m64n128k16.f32.bf16.bf16 " REGS64 ", %64, %65, p, 1, 1, %67, %68;\n}\n"
        : ACC64(d) : "l"(da), "l"(db), "r"(scale_d), "n"(TA), "n"(TB));
}
template <int TB>
__device__ __forceinline__ void wgmma_rs_n128(float (&d)[64], uint32_t a0, uint32_t a1, uint32_t a2, uint32_t a3,
                                              uint64_t db, int scale_d) {
    asm volatile(
        "{\n.reg .pred p;\nsetp.ne.b32 p, %69, 0;\n"
        "wgmma.mma_async.sync.aligned.m64n128k16.f32.bf16.bf16 " REGS64 ", {%64, %65, %66, %67}, %68, p, 1, 1, %70;\n}\n"
        : ACC64(d) : "r"(a0), "r"(a1), "r"(a2), "r"(a3), "l"(db), "r"(scale_d), "n"(TB));
}

#define ACC72(d) ACC64(d), \
    "+f"(d[64]), "+f"(d[65]), "+f"(d[66]), "+f"(d[67]), "+f"(d[68]), "+f"(d[69]), "+f"(d[70]), "+f"(d[71])
#define REGS72 "{%0, %1, %2, %3, %4, %5, %6, %7, %8, %9, %10, %11, %12, %13, %14, %15, " \
    "%16, %17, %18, %19, %20, %21, %22, %23, %24, %25, %26, %27, %28, %29, %30, %31, " \
    "%32, %33, %34, %35, %36, %37, %38, %39, %40, %41, %42, %43, %44, %45, %46, %47, " \
    "%48, %49, %50, %51, %52, %53, %54, %55, %56, %57, %58, %59, %60, %61, %62, %63, " \
    "%64, %65, %66, %67, %68, %69, %70, %71}"
template <int TA, int TB>
__device__ __forceinline__ void wgmma_ss_n144(float (&d)[72], uint64_t da, uint64_t db, int scale_d) {
    asm volatile(
        "{\n.reg .pred p;\nsetp.ne.b32 p, %74, 0;\n"
        "wgmma.mma_async.sync.aligned.m64n144k16.f32.bf16.bf16 " REGS72 ", %72, %73, p, 1, 1, %75, %76;\n}\n"
        : ACC72(d) : "l"(da), "l"(db), "r"(scale_d), "n"(TA), "n"(TB));
}

__device__ __forceinline__ uint32_t pack_bf16(float lo, float hi) {
    __nv_bfloat162 v = __floats2bfloat162_rn(lo, hi);
    return *reinterpret_cast<uint32_t*>(&v);
}

constexpr int K1_STAGES = 5;
constexpr int STAGE_BYTES = 34816;
constexpr int X_CHUNK_BYTES = SQ * 64 * 2;
constexpr int K1_Q_OFF = K1_STAGES * STAGE_BYTES;
constexpr int K1_BAR_OFF = K1_Q_OFF + 3 * 16384;
constexpr int K1_SMEM = K1_BAR_OFF + 256 + 1024;

struct K1Maps {
    CUtensorMap x[2], wq[2], k[2], v[2], o;
};

__global__ void __launch_bounds__(512, 1)
attn_kernel(const __grid_constant__ K1Maps maps)
{
    extern __shared__ uint8_t smem_raw[];
    uint32_t sbase = (smem_u32(smem_raw) + 1023) & ~1023u;
    const uint32_t bar_full = sbase + K1_BAR_OFF;
    const uint32_t bar_empty = bar_full + 8 * K1_STAGES;
    const int tid = threadIdx.x;
    const int wg = tid >> 7;

    if (tid == 0) {
        for (int s = 0; s < K1_STAGES; s++) {
            mbar_init(bar_full + 8 * s, 1);
            mbar_init(bar_empty + 8 * s, 3);
        }
        asm volatile("fence.mbarrier_init.release.cluster;" ::: "memory");
    }
    __syncthreads();

    if (wg == 0) {
        reg_dealloc<32>();
        if (tid == 0) {
            int stage = 0; uint32_t phase = 1;
            for (int item = blockIdx.x; item < N_ITEMS; item += gridDim.x) {
                const int blk = item >> 9;
                const int b = (item >> 5) & 15;
                const int h = item & 31;
                for (int c = 0; c < 8; c++) {
                    mbar_wait(bar_empty + 8 * stage, phase);
                    const uint32_t dst = sbase + stage * STAGE_BYTES;
                    const uint32_t fb = bar_full + 8 * stage;
                    mbar_expect_tx(fb, STAGE_BYTES);
                    tma_load_2d(dst, &maps.x[blk], fb, c * 64, b * SQ);
                    tma_load_2d(dst + X_CHUNK_BYTES, &maps.wq[blk], fb, h * DH, c * 64);
                    tma_load_2d(dst + X_CHUNK_BYTES + 8192, &maps.wq[blk], fb, h * DH + 64, c * 64);
                    if (++stage == K1_STAGES) { stage = 0; phase ^= 1; }
                }
                const int row0 = (b * NH + h) * SK;
                for (int j = 0; j < 8; j++) {
                    mbar_wait(bar_empty + 8 * stage, phase);
                    const uint32_t dst = sbase + stage * STAGE_BYTES;
                    const uint32_t fb = bar_full + 8 * stage;
                    mbar_expect_tx(fb, 32768);
                    const CUtensorMap* m = (j & 1) ? &maps.v[blk] : &maps.k[blk];
                    const int r = row0 + (j >> 1) * 128;
                    tma_load_2d(dst, m, fb, 0, r);
                    tma_load_2d(dst + 16384, m, fb, 64, r);
                    if (++stage == K1_STAGES) { stage = 0; phase ^= 1; }
                }
            }
        }
    } else {
        reg_alloc<160>();
        const int w = wg - 1;
        const int t = tid & 127;
        const int warp = t >> 5;
        const int lane = t & 31;
        const int r0 = warp * 16 + (lane >> 2);
        const int cq = (lane & 3) * 2;
        const uint32_t qbase = sbase + K1_Q_OFF + w * 16384;
        const float sl2 = 0.08838834764831845f * 1.4426950408889634f;

        int stage = 0; uint32_t phase = 0;
        for (int item = blockIdx.x; item < N_ITEMS; item += gridDim.x) {
            const int blk = item >> 9;
            const int b = (item >> 5) & 15;
            const int h = item & 31;

            float o[64];
            {
                int prev_stage = -1;
                for (int c = 0; c < 8; c++) {
                    mbar_wait(bar_full + 8 * stage, phase);
                    const uint32_t st = sbase + stage * STAGE_BYTES;
                    wgmma_fence();
#pragma unroll
                    for (int kk = 0; kk < 4; kk++) {
                        uint64_t da = make_desc(st + w * 8192 + kk * 32, 16, 1024);
                        uint64_t db = make_desc(st + X_CHUNK_BYTES + kk * 2048, 8192, 1024);
                        wgmma_ss_n128<0, 1>(o, da, db, (c | kk) != 0);
                    }
                    wgmma_commit();
                    if (prev_stage >= 0) {
                        wgmma_wait<1>();
                        if (t == 0) mbar_arrive(bar_empty + 8 * prev_stage);
                    }
                    prev_stage = stage;
                    if (++stage == K1_STAGES) { stage = 0; phase ^= 1; }
                }
                wgmma_wait<0>();
                if (t == 0) { mbar_arrive(bar_empty + 8 * prev_stage); bulk_wait_read0(); }
                named_bar_sync(1 + w, 128);
#pragma unroll
                for (int j = 0; j < 16; j++) {
                    const int blkc = j >> 3;
                    const int g = j & 7;
                    uint32_t a0 = qbase + blkc * 8192 + r0 * 128 + ((g ^ (r0 & 7)) << 4) + cq * 2;
                    uint32_t a1 = qbase + blkc * 8192 + (r0 + 8) * 128 + ((g ^ (r0 & 7)) << 4) + cq * 2;
                    uint32_t v0 = pack_bf16(o[4 * j], o[4 * j + 1]);
                    uint32_t v1 = pack_bf16(o[4 * j + 2], o[4 * j + 3]);
                    asm volatile("st.shared.b32 [%0], %1;" :: "r"(a0), "r"(v0) : "memory");
                    asm volatile("st.shared.b32 [%0], %1;" :: "r"(a1), "r"(v1) : "memory");
                }
                fence_proxy_async();
                named_bar_sync(1 + w, 128);
            }

            float m0 = -INFINITY, m1 = -INFINITY, l0 = 0.f, l1 = 0.f;
            for (int j = 0; j < 4; j++) {
                float s[64];
                mbar_wait(bar_full + 8 * stage, phase);
                {
                    const uint32_t st = sbase + stage * STAGE_BYTES;
                    wgmma_fence();
#pragma unroll
                    for (int kk = 0; kk < 8; kk++) {
                        uint64_t da = make_desc(qbase + (kk >> 2) * 8192 + (kk & 3) * 32, 16, 1024);
                        uint64_t db = make_desc(st + (kk >> 2) * 16384 + (kk & 3) * 32, 16, 1024);
                        wgmma_ss_n128<0, 0>(s, da, db, kk != 0);
                    }
                    wgmma_commit();
                    wgmma_wait<0>();
                    if (t == 0) mbar_arrive(bar_empty + 8 * stage);
                    if (++stage == K1_STAGES) { stage = 0; phase ^= 1; }
                }
                float mx0 = m0, mx1 = m1;
#pragma unroll
                for (int i = 0; i < 16; i++) {
                    mx0 = fmaxf(mx0, fmaxf(s[4 * i], s[4 * i + 1]));
                    mx1 = fmaxf(mx1, fmaxf(s[4 * i + 2], s[4 * i + 3]));
                }
                mx0 = fmaxf(mx0, __shfl_xor_sync(0xffffffffu, mx0, 1));
                mx0 = fmaxf(mx0, __shfl_xor_sync(0xffffffffu, mx0, 2));
                mx1 = fmaxf(mx1, __shfl_xor_sync(0xffffffffu, mx1, 1));
                mx1 = fmaxf(mx1, __shfl_xor_sync(0xffffffffu, mx1, 2));
                const float a0 = exp2f((m0 - mx0) * sl2);
                const float a1 = exp2f((m1 - mx1) * sl2);
                m0 = mx0; m1 = mx1;
                const float ms0 = mx0 * sl2, ms1 = mx1 * sl2;
                float sum0 = 0.f, sum1 = 0.f;
                uint32_t p[32];
#pragma unroll
                for (int i = 0; i < 16; i++) {
                    float e0 = exp2f(fmaf(s[4 * i], sl2, -ms0));
                    float e1 = exp2f(fmaf(s[4 * i + 1], sl2, -ms0));
                    float e2 = exp2f(fmaf(s[4 * i + 2], sl2, -ms1));
                    float e3 = exp2f(fmaf(s[4 * i + 3], sl2, -ms1));
                    sum0 += e0 + e1;
                    sum1 += e2 + e3;
                    p[2 * i] = pack_bf16(e0, e1);
                    p[2 * i + 1] = pack_bf16(e2, e3);
                }
                l0 = l0 * a0 + sum0;
                l1 = l1 * a1 + sum1;
                if (j > 0) {
#pragma unroll
                    for (int i = 0; i < 16; i++) {
                        o[4 * i] *= a0; o[4 * i + 1] *= a0;
                        o[4 * i + 2] *= a1; o[4 * i + 3] *= a1;
                    }
                }
                mbar_wait(bar_full + 8 * stage, phase);
                {
                    const uint32_t st = sbase + stage * STAGE_BYTES;
                    wgmma_fence();
#pragma unroll
                    for (int kk = 0; kk < 8; kk++) {
                        uint64_t db = make_desc(st + kk * 2048, 16384, 1024);
                        wgmma_rs_n128<1>(o, p[4 * kk], p[4 * kk + 1], p[4 * kk + 2], p[4 * kk + 3], db, (j | kk) != 0);
                    }
                    wgmma_commit();
                    wgmma_wait<0>();
                    if (t == 0) mbar_arrive(bar_empty + 8 * stage);
                    if (++stage == K1_STAGES) { stage = 0; phase ^= 1; }
                }
            }
            l0 += __shfl_xor_sync(0xffffffffu, l0, 1);
            l0 += __shfl_xor_sync(0xffffffffu, l0, 2);
            l1 += __shfl_xor_sync(0xffffffffu, l1, 1);
            l1 += __shfl_xor_sync(0xffffffffu, l1, 2);
            const float inv0 = 1.f / l0, inv1 = 1.f / l1;
#pragma unroll
            for (int j = 0; j < 16; j++) {
                const int blkc = j >> 3;
                const int g = j & 7;
                uint32_t a0 = qbase + blkc * 8192 + r0 * 128 + ((g ^ (r0 & 7)) << 4) + cq * 2;
                uint32_t a1 = qbase + blkc * 8192 + (r0 + 8) * 128 + ((g ^ (r0 & 7)) << 4) + cq * 2;
                uint32_t v0 = pack_bf16(o[4 * j] * inv0, o[4 * j + 1] * inv0);
                uint32_t v1 = pack_bf16(o[4 * j + 2] * inv1, o[4 * j + 3] * inv1);
                asm volatile("st.shared.b32 [%0], %1;" :: "r"(a0), "r"(v0) : "memory");
                asm volatile("st.shared.b32 [%0], %1;" :: "r"(a1), "r"(v1) : "memory");
            }
            fence_proxy_async();
            named_bar_sync(1 + w, 128);
            if (t == 0) {
                tma_store_3d(&maps.o, qbase, h * DH, w * 64, blk * NB + b);
                tma_store_3d(&maps.o, qbase + 8192, h * DH + 64, w * 64, blk * NB + b);
                bulk_commit();
            }
        }
        if (t == 0) bulk_wait0();
    }
}

constexpr int K2_STAGES = 6;
constexpr int K2_BAR_OFF = K2_STAGES * STAGE_BYTES;
constexpr int K2_SMEM = K2_BAR_OFF + 256 + 1024;

struct K2Maps {
    CUtensorMap wo[2], o;
};

__global__ void __launch_bounds__(384, 1)
oproj_kernel(const __grid_constant__ K2Maps maps, __nv_bfloat16* __restrict__ out)
{
    extern __shared__ uint8_t smem_raw[];
    uint32_t sbase = (smem_u32(smem_raw) + 1023) & ~1023u;
    uint8_t* sgen = smem_raw + (sbase - smem_u32(smem_raw));
    const uint32_t bar_full = sbase + K2_BAR_OFF;
    const uint32_t bar_empty = bar_full + 8 * K2_STAGES;
    const int tid = threadIdx.x;
    const int wg = tid >> 7;
    const int blk = blockIdx.x >> 6;
    const int b = (blockIdx.x >> 2) & 15;
    const int ns = blockIdx.x & 3;

    if (tid == 0) {
        for (int s = 0; s < K2_STAGES; s++) {
            mbar_init(bar_full + 8 * s, 1);
            mbar_init(bar_empty + 8 * s, 2);
        }
        asm volatile("fence.mbarrier_init.release.cluster;" ::: "memory");
    }
    __syncthreads();

    if (wg == 0) {
        if (tid == 0) {
            int stage = 0; uint32_t phase = 1;
            for (int c = 0; c < 64; c++) {
                mbar_wait(bar_empty + 8 * stage, phase);
                const uint32_t dst = sbase + stage * STAGE_BYTES;
                const uint32_t fb = bar_full + 8 * stage;
                mbar_expect_tx(fb, STAGE_BYTES);
                tma_load_3d(dst, &maps.o, fb, c * 64, 0, blk * NB + b);
                tma_load_2d(dst + X_CHUNK_BYTES, &maps.wo[blk], fb, ns * 128, c * 64);
                tma_load_2d(dst + X_CHUNK_BYTES + 8192, &maps.wo[blk], fb, ns * 128 + 64, c * 64);
                if (++stage == K2_STAGES) { stage = 0; phase ^= 1; }
            }
        }
    } else {
        const int w = wg - 1;
        const int t = tid & 127;
        const int warp = t >> 5;
        const int lane = t & 31;
        float acc[72];
        int stage = 0; uint32_t phase = 0;
        int prev_stage = -1;
        for (int c = 0; c < 64; c++) {
            mbar_wait(bar_full + 8 * stage, phase);
            const uint32_t st = sbase + stage * STAGE_BYTES;
            wgmma_fence();
#pragma unroll
            for (int kk = 0; kk < 4; kk++) {
                uint64_t da = make_desc(st + X_CHUNK_BYTES + w * 8192 + kk * 2048, 8192, 1024);
                uint64_t db = make_desc(st + kk * 32, 16, 1024);
                wgmma_ss_n144<1, 0>(acc, da, db, (c | kk) != 0);
            }
            wgmma_commit();
            if (prev_stage >= 0) {
                wgmma_wait<1>();
                if (t == 0) mbar_arrive(bar_empty + 8 * prev_stage);
            }
            prev_stage = stage;
            if (++stage == K2_STAGES) { stage = 0; phase ^= 1; }
        }
        wgmma_wait<0>();
        named_bar_sync(1, 256);
        constexpr int PITCH = 272;
        const int m0 = w * 64 + warp * 16 + (lane >> 2);
#pragma unroll
        for (int j = 0; j < 18; j++) {
            const int n = j * 8 + (lane & 3) * 2;
            __nv_bfloat16* p0 = reinterpret_cast<__nv_bfloat16*>(sgen + n * PITCH) + m0;
            __nv_bfloat16* p1 = reinterpret_cast<__nv_bfloat16*>(sgen + (n + 1) * PITCH) + m0;
            p0[0] = __float2bfloat16(acc[4 * j]);
            p1[0] = __float2bfloat16(acc[4 * j + 1]);
            p0[8] = __float2bfloat16(acc[4 * j + 2]);
            p1[8] = __float2bfloat16(acc[4 * j + 3]);
        }
        named_bar_sync(1, 256);
        const int tt = tid - 128;
        __nv_bfloat16* obase = out + (size_t)(b * SQ) * 1024 + blk * 512 + ns * 128;
        for (int i = tt; i < SQ * 16; i += 256) {
            const int n = i >> 4, g = i & 15;
            uint4 v = *reinterpret_cast<const uint4*>(sgen + n * PITCH + g * 16);
            *reinterpret_cast<uint4*>(obase + (size_t)n * 1024 + g * 8) = v;
        }
    }
}

typedef CUresult (*EncodeFn)(CUtensorMap*, CUtensorMapDataType, cuuint32_t, void*, const cuuint64_t*,
                             const cuuint64_t*, const cuuint32_t*, const cuuint32_t*, CUtensorMapInterleave,
                             CUtensorMapSwizzle, CUtensorMapL2promotion, CUtensorMapFloatOOBfill);

static void make_map(EncodeFn fn, CUtensorMap* m, const void* ptr, int rank, const uint64_t* dims,
                     const uint32_t* box) {
    cuuint64_t gd[3]; cuuint64_t gs[2]; cuuint32_t bx[3]; cuuint32_t es[3] = {1, 1, 1};
    uint64_t stride = 2;
    for (int i = 0; i < rank; i++) {
        gd[i] = dims[i]; bx[i] = box[i];
        stride *= dims[i];
        if (i < rank - 1) gs[i] = stride;
    }
    fn(m, CU_TENSOR_MAP_DATA_TYPE_BFLOAT16, rank, const_cast<void*>(ptr), gd, gs, bx, es,
       CU_TENSOR_MAP_INTERLEAVE_NONE, CU_TENSOR_MAP_SWIZZLE_128B, CU_TENSOR_MAP_L2_PROMOTION_L2_256B,
       CU_TENSOR_MAP_FLOAT_OOB_FILL_NONE);
}

extern "C" void kernel_launch(void* const* d_in, const int* in_sizes, int n_in,
                              void* d_out, int out_size) {
    static K1Maps m1;
    static K2Maps m2;
    static bool init = false;
    if (!init) {
        void* fnp = nullptr;
        cudaDriverEntryPointQueryResult qres;
        cudaGetDriverEntryPoint("cuTensorMapEncodeTiled", &fnp, cudaEnableDefault, &qres);
        EncodeFn fn = (EncodeFn)fnp;
        void* optr = nullptr;
        cudaGetSymbolAddress(&optr, g_o);
        for (int blk = 0; blk < 2; blk++) {
            const void* x = d_in[blk * 5 + 0];
            const void* kc = d_in[blk * 5 + 1];
            const void* vc = d_in[blk * 5 + 2];
            const void* wq = d_in[blk * 5 + 3];
            const void* wo = d_in[blk * 5 + 4];
            { uint64_t d[2] = {DM, (uint64_t)NB * SQ}; uint32_t bx[2] = {64, SQ}; make_map(fn, &m1.x[blk], x, 2, d, bx); }
            { uint64_t d[2] = {HD, DM}; uint32_t bx[2] = {64, 64}; make_map(fn, &m1.wq[blk], wq, 2, d, bx); }
            { uint64_t d[2] = {DH, (uint64_t)NB * NH * SK}; uint32_t bx[2] = {64, 128}; make_map(fn, &m1.k[blk], kc, 2, d, bx); }
            { uint64_t d[2] = {DH, (uint64_t)NB * NH * SK}; uint32_t bx[2] = {64, 128}; make_map(fn, &m1.v[blk], vc, 2, d, bx); }
            { uint64_t d[2] = {DM, HD}; uint32_t bx[2] = {64, 64}; make_map(fn, &m2.wo[blk], wo, 2, d, bx); }
        }
        { uint64_t d[3] = {HD, SQ, 2 * NB}; uint32_t bx[3] = {64, 64, 1}; make_map(fn, &m1.o, optr, 3, d, bx); }
        { uint64_t d[3] = {HD, SQ, 2 * NB}; uint32_t bx[3] = {64, SQ, 1}; make_map(fn, &m2.o, optr, 3, d, bx); }
        cudaFuncSetAttribute(attn_kernel, cudaFuncAttributeMaxDynamicSharedMemorySize, K1_SMEM);
        cudaFuncSetAttribute(oproj_kernel, cudaFuncAttributeMaxDynamicSharedMemorySize, K2_SMEM);
        init = true;
    }
    attn_kernel<<<132, 512, K1_SMEM>>>(m1);
    oproj_kernel<<<128, 384, K2_SMEM>>>(m2, (__nv_bfloat16*)d_out);
}
```

```cpp
#include <cuda_runtime.h>
#include <cuda_bf16.h>
#include <cuda.h>
#include <stdint.h>

constexpr int NB = 16;
constexpr int SQ = 144;
constexpr int DM = 512;
constexpr int NH = 32;
constexpr int SK = 512;
constexpr int DH = 128;
constexpr int HD = NH * DH;
constexpr int N_ITEMS = 2 * NB * NH;

__device__ __nv_bfloat16 g_o[2 * NB * SQ * HD];

__device__ __forceinline__ uint32_t smem_u32(const void* p) {
    return (uint32_t)__cvta_generic_to_shared(p);
}
__device__ __forceinline__ void mbar_init(uint32_t bar, uint32_t count) {
    asm volatile("mbarrier.init.shared::cta.b64 [%0], %1;" :: "r"(bar), "r"(count));
}
__device__ __forceinline__ void mbar_expect_tx(uint32_t bar, uint32_t bytes) {
    asm volatile("mbarrier.arrive.expect_tx.shared::cta.b64 _, [%0], %1;" :: "r"(bar), "r"(bytes) : "memory");
}
__device__ __forceinline__ void mbar_arrive(uint32_t bar) {
    asm volatile("mbarrier.arrive.shared::cta.b64 _, [%0];" :: "r"(bar) : "memory");
}
__device__ __forceinline__ void mbar_wait(uint32_t bar, uint32_t parity) {
    asm volatile(
        "{\n"
        ".reg .pred p;\n"
        "LAB_WAIT:\n"
        "mbarrier.try_wait.parity.shared::cta.b64 p, [%0], %1;\n"
        "@p bra LAB_DONE;\n"
        "bra LAB_WAIT;\n"
        "LAB_DONE:\n"
        "}\n" :: "r"(bar), "r"(parity) : "memory");
}
__device__ __forceinline__ void tma_load_2d(uint32_t dst, const CUtensorMap* map, uint32_t bar, int c0, int c1) {
    asm volatile(
        "cp.async.bulk.tensor.2d.shared::cluster.global.mbarrier::complete_tx::bytes [%0], [%1, {%3, %4}], [%2];"
        :: "r"(dst), "l"(map), "r"(bar), "r"(c0), "r"(c1) : "memory");
}
__device__ __forceinline__ void tma_load_2d_mc(uint32_t dst, const CUtensorMap* map, uint32_t bar, int c0, int c1, uint16_t mask) {
    asm volatile(
        "cp.async.bulk.tensor.2d.shared::cluster.global.mbarrier::complete_tx::bytes.multicast::cluster [%0], [%1, {%3, %4}], [%2], %5;"
        :: "r"(dst), "l"(map), "r"(bar), "r"(c0), "r"(c1), "h"(mask) : "memory");
}
__device__ __forceinline__ void mbar_arrive_cluster(uint32_t bar, uint32_t cta) {
    asm volatile(
        "{\n.reg .b32 ra;\n"
        "mapa.shared::cluster.u32 ra, %0, %1;\n"
        "mbarrier.arrive.release.cluster.shared::cluster.b64 _, [ra];\n}\n"
        :: "r"(bar), "r"(cta) : "memory");
}
__device__ __forceinline__ void cluster_sync_all() {
    asm volatile("barrier.cluster.arrive.release.aligned;\nbarrier.cluster.wait.acquire.aligned;" ::: "memory");
}
__device__ __forceinline__ uint32_t cluster_rank() {
    uint32_t r; asm volatile("mov.u32 %0, %%cluster_ctarank;" : "=r"(r)); return r;
}
__device__ __forceinline__ void tma_load_3d(uint32_t dst, const CUtensorMap* map, uint32_t bar, int c0, int c1, int c2) {
    asm volatile(
        "cp.async.bulk.tensor.3d.shared::cluster.global.mbarrier::complete_tx::bytes [%0], [%1, {%3, %4, %5}], [%2];"
        :: "r"(dst), "l"(map), "r"(bar), "r"(c0), "r"(c1), "r"(c2) : "memory");
}
__device__ __forceinline__ void tma_store_3d(const CUtensorMap* map, uint32_t src, int c0, int c1, int c2) {
    asm volatile(
        "cp.async.bulk.tensor.3d.global.shared::cta.bulk_group [%0, {%2, %3, %4}], [%1];"
        :: "l"(map), "r"(src), "r"(c0), "r"(c1), "r"(c2) : "memory");
}
__device__ __forceinline__ void bulk_commit() { asm volatile("cp.async.bulk.commit_group;" ::: "memory"); }
__device__ __forceinline__ void bulk_wait_read0() { asm volatile("cp.async.bulk.wait_group.read 0;" ::: "memory"); }
__device__ __forceinline__ void bulk_wait0() { asm volatile("cp.async.bulk.wait_group 0;" ::: "memory"); }
__device__ __forceinline__ void fence_proxy_async() { asm volatile("fence.proxy.async.shared::cta;" ::: "memory"); }
__device__ __forceinline__ void named_bar_sync(int id, int nthreads) {
    asm volatile("bar.sync %0, %1;" :: "r"(id), "r"(nthreads) : "memory");
}
__device__ __forceinline__ void wgmma_fence() { asm volatile("wgmma.fence.sync.aligned;" ::: "memory"); }
__device__ __forceinline__ void wgmma_commit() { asm volatile("wgmma.commit_group.sync.aligned;" ::: "memory"); }
template <int N> __device__ __forceinline__ void wgmma_wait() {
    asm volatile("wgmma.wait_group.sync.aligned %0;" :: "n"(N) : "memory");
}
template <int R> __device__ __forceinline__ void reg_alloc() { asm volatile("setmaxnreg.inc.sync.aligned.u32 %0;" :: "n"(R)); }
template <int R> __device__ __forceinline__ void reg_dealloc() { asm volatile("setmaxnreg.dec.sync.aligned.u32 %0;" :: "n"(R)); }

__device__ __forceinline__ uint64_t make_desc(uint32_t addr, uint32_t lbo, uint32_t sbo) {
    uint64_t d = 0;
    d |= (uint64_t)((addr & 0x3FFFF) >> 4);
    d |= (uint64_t)((lbo & 0x3FFFF) >> 4) << 16;
    d |= (uint64_t)((sbo & 0x3FFFF) >> 4) << 32;
    d |= (uint64_t)1 << 62;
    return d;
}

#define ACC64(d) \
    "+f"(d[0]), "+f"(d[1]), "+f"(d[2]), "+f"(d[3]), "+f"(d[4]), "+f"(d[5]), "+f"(d[6]), "+f"(d[7]), \
    "+f"(d[8]), "+f"(d[9]), "+f"(d[10]), "+f"(d[11]), "+f"(d[12]), "+f"(d[13]), "+f"(d[14]), "+f"(d[15]), \
    "+f"(d[16]), "+f"(d[17]), "+f"(d[18]), "+f"(d[19]), "+f"(d[20]), "+f"(d[21]), "+f"(d[22]), "+f"(d[23]), \
    "+f"(d[24]), "+f"(d[25]), "+f"(d[26]), "+f"(d[27]), "+f"(d[28]), "+f"(d[29]), "+f"(d[30]), "+f"(d[31]), \
    "+f"(d[32]), "+f"(d[33]), "+f"(d[34]), "+f"(d[35]), "+f"(d[36]), "+f"(d[37]), "+f"(d[38]), "+f"(d[39]), \
    "+f"(d[40]), "+f"(d[41]), "+f"(d[42]), "+f"(d[43]), "+f"(d[44]), "+f"(d[45]), "+f"(d[46]), "+f"(d[47]), \
    "+f"(d[48]), "+f"(d[49]), "+f"(d[50]), "+f"(d[51]), "+f"(d[52]), "+f"(d[53]), "+f"(d[54]), "+f"(d[55]), \
    "+f"(d[56]), "+f"(d[57]), "+f"(d[58]), "+f"(d[59]), "+f"(d[60]), "+f"(d[61]), "+f"(d[62]), "+f"(d[63])

#define REGS64 "{%0, %1, %2, %3, %4, %5, %6, %7, %8, %9, %10, %11, %12, %13, %14, %15, " \
    "%16, %17, %18, %19, %20, %21, %22, %23, %24, %25, %26, %27, %28, %29, %30, %31, " \
    "%32, %33, %34, %35, %36, %37, %38, %39, %40, %41, %42, %43, %44, %45, %46, %47, " \
    "%48, %49, %50, %51, %52, %53, %54, %55, %56, %57, %58, %59, %60, %61, %62, %63}"

template <int TA, int TB>
__device__ __forceinline__ void wgmma_ss_n128(float (&d)[64], uint64_t da, uint64_t db, int scale_d) {
    asm volatile(
        "{\n.reg .pred p;\nsetp.ne.b32 p, %66, 0;\n"
        "wgmma.mma_async.sync.aligned.m64n128k16.f32.bf16.bf16 " REGS64 ", %64, %65, p, 1, 1, %67, %68;\n}\n"
        : ACC64(d) : "l"(da), "l"(db), "r"(scale_d), "n"(TA), "n"(TB));
}
template <int TB>
__device__ __forceinline__ void wgmma_rs_n128(float (&d)[64], uint32_t a0, uint32_t a1, uint32_t a2, uint32_t a3,
                                              uint64_t db, int scale_d) {
    asm volatile(
        "{\n.reg .pred p;\nsetp.ne.b32 p, %69, 0;\n"
        "wgmma.mma_async.sync.aligned.m64n128k16.f32.bf16.bf16 " REGS64 ", {%64, %65, %66, %67}, %68, p, 1, 1, %70;\n}\n"
        : ACC64(d) : "r"(a0), "r"(a1), "r"(a2), "r"(a3), "l"(db), "r"(scale_d), "n"(TB));
}

#define ACC72(d) ACC64(d), \
    "+f"(d[64]), "+f"(d[65]), "+f"(d[66]), "+f"(d[67]), "+f"(d[68]), "+f"(d[69]), "+f"(d[70]), "+f"(d[71])
#define REGS72 "{%0, %1, %2, %3, %4, %5, %6, %7, %8, %9, %10, %11, %12, %13, %14, %15, " \
    "%16, %17, %18, %19, %20, %21, %22, %23, %24, %25, %26, %27, %28, %29, %30, %31, " \
    "%32, %33, %34, %35, %36, %37, %38, %39, %40, %41, %42, %43, %44, %45, %46, %47, " \
    "%48, %49, %50, %51, %52, %53, %54, %55, %56, %57, %58, %59, %60, %61, %62, %63, " \
    "%64, %65, %66, %67, %68, %69, %70, %71}"
template <int TA, int TB>
__device__ __forceinline__ void wgmma_ss_n144(float (&d)[72], uint64_t da, uint64_t db, int scale_d) {
    asm volatile(
        "{\n.reg .pred p;\nsetp.ne.b32 p, %74, 0;\n"
        "wgmma.mma_async.sync.aligned.m64n144k16.f32.bf16.bf16 " REGS72 ", %72, %73, p, 1, 1, %75, %76;\n}\n"
        : ACC72(d) : "l"(da), "l"(db), "r"(scale_d), "n"(TA), "n"(TB));
}

__device__ __forceinline__ uint32_t pack_bf16(float lo, float hi) {
    __nv_bfloat162 v = __floats2bfloat162_rn(lo, hi);
    return *reinterpret_cast<uint32_t*>(&v);
}

constexpr int K1_STAGES = 5;
constexpr int STAGE_BYTES = 34816;
constexpr int X_CHUNK_BYTES = SQ * 64 * 2;
constexpr int K1_Q_OFF = K1_STAGES * STAGE_BYTES;
constexpr int K1_BAR_OFF = K1_Q_OFF + 3 * 16384;
constexpr int K1_SMEM = K1_BAR_OFF + 256 + 1024;

struct K1Maps {
    CUtensorMap x[2], wq[2], k[2], v[2], o;
};

__global__ void __cluster_dims__(2, 1, 1) __launch_bounds__(512, 1)
attn_kernel(const __grid_constant__ K1Maps maps)
{
    extern __shared__ uint8_t smem_raw[];
    uint32_t sbase = (smem_u32(smem_raw) + 1023) & ~1023u;
    const uint32_t bar_full = sbase + K1_BAR_OFF;
    const uint32_t bar_empty = bar_full + 8 * K1_STAGES;
    const int tid = threadIdx.x;
    const int wg = tid >> 7;

    if (tid == 0) {
        for (int s = 0; s < K1_STAGES; s++) {
            mbar_init(bar_full + 8 * s, 1);
            mbar_init(bar_empty + 8 * s, 6);
        }
        asm volatile("fence.mbarrier_init.release.cluster;" ::: "memory");
    }
    __syncthreads();
    cluster_sync_all();
    const uint32_t crank = cluster_rank();
    const int pair0 = blockIdx.x >> 1;
    const int npairs = gridDim.x >> 1;

    if (wg == 0) {
        reg_dealloc<32>();
        if (tid == 0) {
            int stage = 0; uint32_t phase = 1;
            for (int pr = pair0; pr < N_ITEMS / 2; pr += npairs) {
                const int item = pr * 2 + crank;
                const int blk = item >> 9;
                const int b = (item >> 5) & 15;
                const int h = item & 31;
                for (int c = 0; c < 8; c++) {
                    mbar_wait(bar_empty + 8 * stage, phase);
                    const uint32_t dst = sbase + stage * STAGE_BYTES;
                    const uint32_t fb = bar_full + 8 * stage;
                    mbar_expect_tx(fb, STAGE_BYTES);
                    tma_load_2d_mc(dst + crank * 9216, &maps.x[blk], fb, c * 64, b * SQ + crank * 72, (uint16_t)3);
                    tma_load_2d(dst + X_CHUNK_BYTES, &maps.wq[blk], fb, h * DH, c * 64);
                    tma_load_2d(dst + X_CHUNK_BYTES + 8192, &maps.wq[blk], fb, h * DH + 64, c * 64);
                    if (++stage == K1_STAGES) { stage = 0; phase ^= 1; }
                }
                const int row0 = (b * NH + h) * SK;
                for (int j = 0; j < 8; j++) {
                    mbar_wait(bar_empty + 8 * stage, phase);
                    const uint32_t dst = sbase + stage * STAGE_BYTES;
                    const uint32_t fb = bar_full + 8 * stage;
                    mbar_expect_tx(fb, 32768);
                    const CUtensorMap* m = (j & 1) ? &maps.v[blk] : &maps.k[blk];
                    const int r = row0 + (j >> 1) * 128;
                    tma_load_2d(dst, m, fb, 0, r);
                    tma_load_2d(dst + 16384, m, fb, 64, r);
                    if (++stage == K1_STAGES) { stage = 0; phase ^= 1; }
                }
            }
        }
    } else {
        reg_alloc<160>();
        const int w = wg - 1;
        const int t = tid & 127;
        const int warp = t >> 5;
        const int lane = t & 31;
        const int r0 = warp * 16 + (lane >> 2);
        const int cq = (lane & 3) * 2;
        const uint32_t qbase = sbase + K1_Q_OFF + w * 16384;
        const float sl2 = 0.08838834764831845f * 1.4426950408889634f;

        int stage = 0; uint32_t phase = 0;
        for (int pr = pair0; pr < N_ITEMS / 2; pr += npairs) {
            const int item = pr * 2 + crank;
            const int blk = item >> 9;
            const int b = (item >> 5) & 15;
            const int h = item & 31;

            float o[64];
            {
                int prev_stage = -1;
                for (int c = 0; c < 8; c++) {
                    mbar_wait(bar_full + 8 * stage, phase);
                    const uint32_t st = sbase + stage * STAGE_BYTES;
                    wgmma_fence();
#pragma unroll
                    for (int kk = 0; kk < 4; kk++) {
                        uint64_t da = make_desc(st + w * 8192 + kk * 32, 16, 1024);
                        uint64_t db = make_desc(st + X_CHUNK_BYTES + kk * 2048, 8192, 1024);
                        wgmma_ss_n128<0, 1>(o, da, db, (c | kk) != 0);
                    }
                    wgmma_commit();
                    if (prev_stage >= 0) {
                        wgmma_wait<1>();
                        if (t < 2) mbar_arrive_cluster(bar_empty + 8 * prev_stage, t);
                    }
                    prev_stage = stage;
                    if (++stage == K1_STAGES) { stage = 0; phase ^= 1; }
                }
                wgmma_wait<0>();
                if (t < 2) mbar_arrive_cluster(bar_empty + 8 * prev_stage, t);
                if (t == 0) bulk_wait_read0();
                named_bar_sync(1 + w, 128);
#pragma unroll
                for (int j = 0; j < 16; j++) {
                    const int blkc = j >> 3;
                    const int g = j & 7;
                    uint32_t a0 = qbase + blkc * 8192 + r0 * 128 + ((g ^ (r0 & 7)) << 4) + cq * 2;
                    uint32_t a1 = qbase + blkc * 8192 + (r0 + 8) * 128 + ((g ^ (r0 & 7)) << 4) + cq * 2;
                    uint32_t v0 = pack_bf16(o[4 * j], o[4 * j + 1]);
                    uint32_t v1 = pack_bf16(o[4 * j + 2], o[4 * j + 3]);
                    asm volatile("st.shared.b32 [%0], %1;" :: "r"(a0), "r"(v0) : "memory");
                    asm volatile("st.shared.b32 [%0], %1;" :: "r"(a1), "r"(v1) : "memory");
                }
                fence_proxy_async();
                named_bar_sync(1 + w, 128);
            }

            float m0 = -INFINITY, m1 = -INFINITY, l0 = 0.f, l1 = 0.f;
            for (int j = 0; j < 4; j++) {
                float s[64];
                mbar_wait(bar_full + 8 * stage, phase);
                {
                    const uint32_t st = sbase + stage * STAGE_BYTES;
                    wgmma_fence();
#pragma unroll
                    for (int kk = 0; kk < 8; kk++) {
                        uint64_t da = make_desc(qbase + (kk >> 2) * 8192 + (kk & 3) * 32, 16, 1024);
                        uint64_t db = make_desc(st + (kk >> 2) * 16384 + (kk & 3) * 32, 16, 1024);
                        wgmma_ss_n128<0, 0>(s, da, db, kk != 0);
                    }
                    wgmma_commit();
                    wgmma_wait<0>();
                    if (t < 2) mbar_arrive_cluster(bar_empty + 8 * stage, t);
                    if (++stage == K1_STAGES) { stage = 0; phase ^= 1; }
                }
                float mx0 = m0, mx1 = m1;
#pragma unroll
                for (int i = 0; i < 16; i++) {
                    mx0 = fmaxf(mx0, fmaxf(s[4 * i], s[4 * i + 1]));
                    mx1 = fmaxf(mx1, fmaxf(s[4 * i + 2], s[4 * i + 3]));
                }
                mx0 = fmaxf(mx0, __shfl_xor_sync(0xffffffffu, mx0, 1));
                mx0 = fmaxf(mx0, __shfl_xor_sync(0xffffffffu, mx0, 2));
                mx1 = fmaxf(mx1, __shfl_xor_sync(0xffffffffu, mx1, 1));
                mx1 = fmaxf(mx1, __shfl_xor_sync(0xffffffffu, mx1, 2));
                const float a0 = exp2f((m0 - mx0) * sl2);
                const float a1 = exp2f((m1 - mx1) * sl2);
                m0 = mx0; m1 = mx1;
                const float ms0 = mx0 * sl2, ms1 = mx1 * sl2;
                float sum0 = 0.f, sum1 = 0.f;
                uint32_t p[32];
#pragma unroll
                for (int i = 0; i < 16; i++) {
                    float e0 = exp2f(fmaf(s[4 * i], sl2, -ms0));
                    float e1 = exp2f(fmaf(s[4 * i + 1], sl2, -ms0));
                    float e2 = exp2f(fmaf(s[4 * i + 2], sl2, -ms1));
                    float e3 = exp2f(fmaf(s[4 * i + 3], sl2, -ms1));
                    sum0 += e0 + e1;
                    sum1 += e2 + e3;
                    p[2 * i] = pack_bf16(e0, e1);
                    p[2 * i + 1] = pack_bf16(e2, e3);
                }
                l0 = l0 * a0 + sum0;
                l1 = l1 * a1 + sum1;
                if (j > 0) {
#pragma unroll
                    for (int i = 0; i < 16; i++) {
                        o[4 * i] *= a0; o[4 * i + 1] *= a0;
                        o[4 * i + 2] *= a1; o[4 * i + 3] *= a1;
                    }
                }
                mbar_wait(bar_full + 8 * stage, phase);
                {
                    const uint32_t st = sbase + stage * STAGE_BYTES;
                    wgmma_fence();
#pragma unroll
                    for (int kk = 0; kk < 8; kk++) {
                        uint64_t db = make_desc(st + kk * 2048, 16384, 1024);
                        wgmma_rs_n128<1>(o, p[4 * kk], p[4 * kk + 1], p[4 * kk + 2], p[4 * kk + 3], db, (j | kk) != 0);
                    }
                    wgmma_commit();
                    wgmma_wait<0>();
                    if (t < 2) mbar_arrive_cluster(bar_empty + 8 * stage, t);
                    if (++stage == K1_STAGES) { stage = 0; phase ^= 1; }
                }
            }
            l0 += __shfl_xor_sync(0xffffffffu, l0, 1);
            l0 += __shfl_xor_sync(0xffffffffu, l0, 2);
            l1 += __shfl_xor_sync(0xffffffffu, l1, 1);
            l1 += __shfl_xor_sync(0xffffffffu, l1, 2);
            const float inv0 = 1.f / l0, inv1 = 1.f / l1;
#pragma unroll
            for (int j = 0; j < 16; j++) {
                const int blkc = j >> 3;
                const int g = j & 7;
                uint32_t a0 = qbase + blkc * 8192 + r0 * 128 + ((g ^ (r0 & 7)) << 4) + cq * 2;
                uint32_t a1 = qbase + blkc * 8192 + (r0 + 8) * 128 + ((g ^ (r0 & 7)) << 4) + cq * 2;
                uint32_t v0 = pack_bf16(o[4 * j] * inv0, o[4 * j + 1] * inv0);
                uint32_t v1 = pack_bf16(o[4 * j + 2] * inv1, o[4 * j + 3] * inv1);
                asm volatile("st.shared.b32 [%0], %1;" :: "r"(a0), "r"(v0) : "memory");
                asm volatile("st.shared.b32 [%0], %1;" :: "r"(a1), "r"(v1) : "memory");
            }
            fence_proxy_async();
            named_bar_sync(1 + w, 128);
            if (t == 0) {
                tma_store_3d(&maps.o, qbase, h * DH, w * 64, blk * NB + b);
                tma_store_3d(&maps.o, qbase + 8192, h * DH + 64, w * 64, blk * NB + b);
                bulk_commit();
            }
        }
        if (t == 0) bulk_wait0();
    }
    cluster_sync_all();
}

constexpr int K2_STAGES = 6;
constexpr int K2_BAR_OFF = K2_STAGES * STAGE_BYTES;
constexpr int K2_SMEM = K2_BAR_OFF + 256 + 1024;

struct K2Maps {
    CUtensorMap wo[2], o;
};

__global__ void __launch_bounds__(384, 1)
oproj_kernel(const __grid_constant__ K2Maps maps, __nv_bfloat16* __restrict__ out)
{
    extern __shared__ uint8_t smem_raw[];
    uint32_t sbase = (smem_u32(smem_raw) + 1023) & ~1023u;
    uint8_t* sgen = smem_raw + (sbase - smem_u32(smem_raw));
    const uint32_t bar_full = sbase + K2_BAR_OFF;
    const uint32_t bar_empty = bar_full + 8 * K2_STAGES;
    const int tid = threadIdx.x;
    const int wg = tid >> 7;
    const int blk = blockIdx.x >> 6;
    const int b = (blockIdx.x >> 2) & 15;
    const int ns = blockIdx.x & 3;

    if (tid == 0) {
        for (int s = 0; s < K2_STAGES; s++) {
            mbar_init(bar_full + 8 * s, 1);
            mbar_init(bar_empty + 8 * s, 2);
        }
        asm volatile("fence.mbarrier_init.release.cluster;" ::: "memory");
    }
    __syncthreads();

    if (wg == 0) {
        if (tid == 0) {
            int stage = 0; uint32_t phase = 1;
            for (int c = 0; c < 64; c++) {
                mbar_wait(bar_empty + 8 * stage, phase);
                const uint32_t dst = sbase + stage * STAGE_BYTES;
                const uint32_t fb = bar_full + 8 * stage;
                mbar_expect_tx(fb, STAGE_BYTES);
                tma_load_3d(dst, &maps.o, fb, c * 64, 0, blk * NB + b);
                tma_load_2d(dst + X_CHUNK_BYTES, &maps.wo[blk], fb, ns * 128, c * 64);
                tma_load_2d(dst + X_CHUNK_BYTES + 8192, &maps.wo[blk], fb, ns * 128 + 64, c * 64);
                if (++stage == K2_STAGES) { stage = 0; phase ^= 1; }
            }
        }
    } else {
        const int w = wg - 1;
        const int t = tid & 127;
        const int warp = t >> 5;
        const int lane = t & 31;
        float acc[72];
        int stage = 0; uint32_t phase = 0;
        int prev_stage = -1;
        for (int c = 0; c < 64; c++) {
            mbar_wait(bar_full + 8 * stage, phase);
            const uint32_t st = sbase + stage * STAGE_BYTES;
            wgmma_fence();
#pragma unroll
            for (int kk = 0; kk < 4; kk++) {
                uint64_t da = make_desc(st + X_CHUNK_BYTES + w * 8192 + kk * 2048, 8192, 1024);
                uint64_t db = make_desc(st + kk * 32, 16, 1024);
                wgmma_ss_n144<1, 0>(acc, da, db, (c | kk) != 0);
            }
            wgmma_commit();
            if (prev_stage >= 0) {
                wgmma_wait<1>();
                if (t == 0) mbar_arrive(bar_empty + 8 * prev_stage);
            }
            prev_stage = stage;
            if (++stage == K2_STAGES) { stage = 0; phase ^= 1; }
        }
        wgmma_wait<0>();
        named_bar_sync(1, 256);
        constexpr int PITCH = 272;
        const int m0 = w * 64 + warp * 16 + (lane >> 2);
#pragma unroll
        for (int j = 0; j < 18; j++) {
            const int n = j * 8 + (lane & 3) * 2;
            __nv_bfloat16* p0 = reinterpret_cast<__nv_bfloat16*>(sgen + n * PITCH) + m0;
            __nv_bfloat16* p1 = reinterpret_cast<__nv_bfloat16*>(sgen + (n + 1) * PITCH) + m0;
            p0[0] = __float2bfloat16(acc[4 * j]);
            p1[0] = __float2bfloat16(acc[4 * j + 1]);
            p0[8] = __float2bfloat16(acc[4 * j + 2]);
            p1[8] = __float2bfloat16(acc[4 * j + 3]);
        }
        named_bar_sync(1, 256);
        const int tt = tid - 128;
        __nv_bfloat16* obase = out + (size_t)(b * SQ) * 1024 + blk * 512 + ns * 128;
        for (int i = tt; i < SQ * 16; i += 256) {
            const int n = i >> 4, g = i & 15;
            uint4 v = *reinterpret_cast<const uint4*>(sgen + n * PITCH + g * 16);
            *reinterpret_cast<uint4*>(obase + (size_t)n * 1024 + g * 8) = v;
        }
    }
}

typedef CUresult (*EncodeFn)(CUtensorMap*, CUtensorMapDataType, cuuint32_t, void*, const cuuint64_t*,
                             const cuuint64_t*, const cuuint32_t*, const cuuint32_t*, CUtensorMapInterleave,
                             CUtensorMapSwizzle, CUtensorMapL2promotion, CUtensorMapFloatOOBfill);

static void make_map(EncodeFn fn, CUtensorMap* m, const void* ptr, int rank, const uint64_t* dims,
                     const uint32_t* box) {
    cuuint64_t gd[3]; cuuint64_t gs[2]; cuuint32_t bx[3]; cuuint32_t es[3] = {1, 1, 1};
    uint64_t stride = 2;
    for (int i = 0; i < rank; i++) {
        gd[i] = dims[i]; bx[i] = box[i];
        stride *= dims[i];
        if (i < rank - 1) gs[i] = stride;
    }
    fn(m, CU_TENSOR_MAP_DATA_TYPE_BFLOAT16, rank, const_cast<void*>(ptr), gd, gs, bx, es,
       CU_TENSOR_MAP_INTERLEAVE_NONE, CU_TENSOR_MAP_SWIZZLE_128B, CU_TENSOR_MAP_L2_PROMOTION_L2_256B,
       CU_TENSOR_MAP_FLOAT_OOB_FILL_NONE);
}

extern "C" void kernel_launch(void* const* d_in, const int* in_sizes, int n_in,
                              void* d_out, int out_size) {
    static K1Maps m1;
    static K2Maps m2;
    static bool init = false;
    if (!init) {
        void* fnp = nullptr;
        cudaDriverEntryPointQueryResult qres;
        cudaGetDriverEntryPoint("cuTensorMapEncodeTiled", &fnp, cudaEnableDefault, &qres);
        EncodeFn fn = (EncodeFn)fnp;
        void* optr = nullptr;
        cudaGetSymbolAddress(&optr, g_o);
        for (int blk = 0; blk < 2; blk++) {
            const void* x = d_in[blk * 5 + 0];
            const void* kc = d_in[blk * 5 + 1];
            const void* vc = d_in[blk * 5 + 2];
            const void* wq = d_in[blk * 5 + 3];
            const void* wo = d_in[blk * 5 + 4];
            { uint64_t d[2] = {DM, (uint64_t)NB * SQ}; uint32_t bx[2] = {64, 72}; make_map(fn, &m1.x[blk], x, 2, d, bx); }
            { uint64_t d[2] = {HD, DM}; uint32_t bx[2] = {64, 64}; make_map(fn, &m1.wq[blk], wq, 2, d, bx); }
            { uint64_t d[2] = {DH, (uint64_t)NB * NH * SK}; uint32_t bx[2] = {64, 128}; make_map(fn, &m1.k[blk], kc, 2, d, bx); }
            { uint64_t d[2] = {DH, (uint64_t)NB * NH * SK}; uint32_t bx[2] = {64, 128}; make_map(fn, &m1.v[blk], vc, 2, d, bx); }
            { uint64_t d[2] = {DM, HD}; uint32_t bx[2] = {64, 64}; make_map(fn, &m2.wo[blk], wo, 2, d, bx); }
        }
        { uint64_t d[3] = {HD, SQ, 2 * NB}; uint32_t bx[3] = {64, 64, 1}; make_map(fn, &m1.o, optr, 3, d, bx); }
        { uint64_t d[3] = {HD, SQ, 2 * NB}; uint32_t bx[3] = {64, SQ, 1}; make_map(fn, &m2.o, optr, 3, d, bx); }
        cudaFuncSetAttribute(attn_kernel, cudaFuncAttributeMaxDynamicSharedMemorySize, K1_SMEM);
        cudaFuncSetAttribute(oproj_kernel, cudaFuncAttributeMaxDynamicSharedMemorySize, K2_SMEM);
        init = true;
    }
    attn_kernel<<<132, 512, K1_SMEM>>>(m1);
    oproj_kernel<<<128, 384, K2_SMEM>>>(m2, (__nv_bfloat16*)d_out);
}
```

```cpp
#include <cuda_runtime.h>
#include <cuda_bf16.h>
#include <cuda.h>
#include <stdint.h>

constexpr int NB = 16;
constexpr int SQ = 144;
constexpr int DM = 512;
constexpr int NH = 32;
constexpr int SK = 512;
constexpr int DH = 128;
constexpr int HD = NH * DH;
constexpr int N_ITEMS = 2 * NB * NH;

__device__ __nv_bfloat16 g_o[2 * NB * SQ * HD];

__device__ __forceinline__ uint32_t smem_u32(const void* p) {
    return (uint32_t)__cvta_generic_to_shared(p);
}
__device__ __forceinline__ void mbar_init(uint32_t bar, uint32_t count) {
    asm volatile("mbarrier.init.shared::cta.b64 [%0], %1;" :: "r"(bar), "r"(count));
}
__device__ __forceinline__ void mbar_expect_tx(uint32_t bar, uint32_t bytes) {
    asm volatile("mbarrier.arrive.expect_tx.shared::cta.b64 _, [%0], %1;" :: "r"(bar), "r"(bytes) : "memory");
}
__device__ __forceinline__ void mbar_arrive(uint32_t bar) {
    asm volatile("mbarrier.arrive.shared::cta.b64 _, [%0];" :: "r"(bar) : "memory");
}
__device__ __forceinline__ void mbar_wait(uint32_t bar, uint32_t parity) {
    asm volatile(
        "{\n"
        ".reg .pred p;\n"
        "LAB_WAIT:\n"
        "mbarrier.try_wait.parity.shared::cta.b64 p, [%0], %1;\n"
        "@p bra LAB_DONE;\n"
        "bra LAB_WAIT;\n"
        "LAB_DONE:\n"
        "}\n" :: "r"(bar), "r"(parity) : "memory");
}
__device__ __forceinline__ void tma_load_2d(uint32_t dst, const CUtensorMap* map, uint32_t bar, int c0, int c1) {
    asm volatile(
        "cp.async.bulk.tensor.2d.shared::cluster.global.mbarrier::complete_tx::bytes [%0], [%1, {%3, %4}], [%2];"
        :: "r"(dst), "l"(map), "r"(bar), "r"(c0), "r"(c1) : "memory");
}
__device__ __forceinline__ void tma_load_2d_mc(uint32_t dst, const CUtensorMap* map, uint32_t bar, int c0, int c1, uint16_t mask) {
    asm volatile(
        "cp.async.bulk.tensor.2d.shared::cluster.global.mbarrier::complete_tx::bytes.multicast::cluster [%0], [%1, {%3, %4}], [%2], %5;"
        :: "r"(dst), "l"(map), "r"(bar), "r"(c0), "r"(c1), "h"(mask) : "memory");
}
__device__ __forceinline__ void mbar_arrive_cluster(uint32_t bar, uint32_t cta) {
    asm volatile(
        "{\n.reg .b32 ra;\n"
        "mapa.shared::cluster.u32 ra, %0, %1;\n"
        "mbarrier.arrive.release.cluster.shared::cluster.b64 _, [ra];\n}\n"
        :: "r"(bar), "r"(cta) : "memory");
}
__device__ __forceinline__ void cluster_sync_all() {
    asm volatile("barrier.cluster.arrive.release.aligned;\nbarrier.cluster.wait.acquire.aligned;" ::: "memory");
}
__device__ __forceinline__ uint32_t cluster_rank() {
    uint32_t r; asm volatile("mov.u32 %0, %%cluster_ctarank;" : "=r"(r)); return r;
}
__device__ __forceinline__ void tma_load_3d(uint32_t dst, const CUtensorMap* map, uint32_t bar, int c0, int c1, int c2) {
    asm volatile(
        "cp.async.bulk.tensor.3d.shared::cluster.global.mbarrier::complete_tx::bytes [%0], [%1, {%3, %4, %5}], [%2];"
        :: "r"(dst), "l"(map), "r"(bar), "r"(c0), "r"(c1), "r"(c2) : "memory");
}
__device__ __forceinline__ void tma_store_3d(const CUtensorMap* map, uint32_t src, int c0, int c1, int c2) {
    asm volatile(
        "cp.async.bulk.tensor.3d.global.shared::cta.bulk_group [%0, {%2, %3, %4}], [%1];"
        :: "l"(map), "r"(src), "r"(c0), "r"(c1), "r"(c2) : "memory");
}
__device__ __forceinline__ void bulk_commit() { asm volatile("cp.async.bulk.commit_group;" ::: "memory"); }
__device__ __forceinline__ void bulk_wait_read0() { asm volatile("cp.async.bulk.wait_group.read 0;" ::: "memory"); }
__device__ __forceinline__ void bulk_wait0() { asm volatile("cp.async.bulk.wait_group 0;" ::: "memory"); }
__device__ __forceinline__ void fence_proxy_async() { asm volatile("fence.proxy.async.shared::cta;" ::: "memory"); }
__device__ __forceinline__ void named_bar_sync(int id, int nthreads) {
    asm volatile("bar.sync %0, %1;" :: "r"(id), "r"(nthreads) : "memory");
}
__device__ __forceinline__ void wgmma_fence() { asm volatile("wgmma.fence.sync.aligned;" ::: "memory"); }
__device__ __forceinline__ void wgmma_commit() { asm volatile("wgmma.commit_group.sync.aligned;" ::: "memory"); }
template <int N> __device__ __forceinline__ void wgmma_wait() {
    asm volatile("wgmma.wait_group.sync.aligned %0;" :: "n"(N) : "memory");
}
template <int R> __device__ __forceinline__ void reg_alloc() { asm volatile("setmaxnreg.inc.sync.aligned.u32 %0;" :: "n"(R)); }
template <int R> __device__ __forceinline__ void reg_dealloc() { asm volatile("setmaxnreg.dec.sync.aligned.u32 %0;" :: "n"(R)); }

__device__ __forceinline__ uint64_t make_desc(uint32_t addr, uint32_t lbo, uint32_t sbo) {
    uint64_t d = 0;
    d |= (uint64_t)((addr & 0x3FFFF) >> 4);
    d |= (uint64_t)((lbo & 0x3FFFF) >> 4) << 16;
    d |= (uint64_t)((sbo & 0x3FFFF) >> 4) << 32;
    d |= (uint64_t)1 << 62;
    return d;
}

#define ACC64(d) \
    "+f"(d[0]), "+f"(d[1]), "+f"(d[2]), "+f"(d[3]), "+f"(d[4]), "+f"(d[5]), "+f"(d[6]), "+f"(d[7]), \
    "+f"(d[8]), "+f"(d[9]), "+f"(d[10]), "+f"(d[11]), "+f"(d[12]), "+f"(d[13]), "+f"(d[14]), "+f"(d[15]), \
    "+f"(d[16]), "+f"(d[17]), "+f"(d[18]), "+f"(d[19]), "+f"(d[20]), "+f"(d[21]), "+f"(d[22]), "+f"(d[23]), \
    "+f"(d[24]), "+f"(d[25]), "+f"(d[26]), "+f"(d[27]), "+f"(d[28]), "+f"(d[29]), "+f"(d[30]), "+f"(d[31]), \
    "+f"(d[32]), "+f"(d[33]), "+f"(d[34]), "+f"(d[35]), "+f"(d[36]), "+f"(d[37]), "+f"(d[38]), "+f"(d[39]), \
    "+f"(d[40]), "+f"(d[41]), "+f"(d[42]), "+f"(d[43]), "+f"(d[44]), "+f"(d[45]), "+f"(d[46]), "+f"(d[47]), \
    "+f"(d[48]), "+f"(d[49]), "+f"(d[50]), "+f"(d[51]), "+f"(d[52]), "+f"(d[53]), "+f"(d[54]), "+f"(d[55]), \
    "+f"(d[56]), "+f"(d[57]), "+f"(d[58]), "+f"(d[59]), "+f"(d[60]), "+f"(d[61]), "+f"(d[62]), "+f"(d[63])

#define REGS64 "{%0, %1, %2, %3, %4, %5, %6, %7, %8, %9, %10, %11, %12, %13, %14, %15, " \
    "%16, %17, %18, %19, %20, %21, %22, %23, %24, %25, %26, %27, %28, %29, %30, %31, " \
    "%32, %33, %34, %35, %36, %37, %38, %39, %40, %41, %42, %43, %44, %45, %46, %47, " \
    "%48, %49, %50, %51, %52, %53, %54, %55, %56, %57, %58, %59, %60, %61, %62, %63}"

template <int TA, int TB>
__device__ __forceinline__ void wgmma_ss_n128(float (&d)[64], uint64_t da, uint64_t db, int scale_d) {
    asm volatile(
        "{\n.reg .pred p;\nsetp.ne.b32 p, %66, 0;\n"
        "wgmma.mma_async.sync.aligned.m64n128k16.f32.bf16.bf16 " REGS64 ", %64, %65, p, 1, 1, %67, %68;\n}\n"
        : ACC64(d) : "l"(da), "l"(db), "r"(scale_d), "n"(TA), "n"(TB));
}
template <int TB>
__device__ __forceinline__ void wgmma_rs_n128(float (&d)[64], uint32_t a0, uint32_t a1, uint32_t a2, uint32_t a3,
                                              uint64_t db, int scale_d) {
    asm volatile(
        "{\n.reg .pred p;\nsetp.ne.b32 p, %69, 0;\n"
        "wgmma.mma_async.sync.aligned.m64n128k16.f32.bf16.bf16 " REGS64 ", {%64, %65, %66, %67}, %68, p, 1, 1, %70;\n}\n"
        : ACC64(d) : "r"(a0), "r"(a1), "r"(a2), "r"(a3), "l"(db), "r"(scale_d), "n"(TB));
}

#define ACC72(d) ACC64(d), \
    "+f"(d[64]), "+f"(d[65]), "+f"(d[66]), "+f"(d[67]), "+f"(d[68]), "+f"(d[69]), "+f"(d[70]), "+f"(d[71])
#define REGS72 "{%0, %1, %2, %3, %4, %5, %6, %7, %8, %9, %10, %11, %12, %13, %14, %15, " \
    "%16, %17, %18, %19, %20, %21, %22, %23, %24, %25, %26, %27, %28, %29, %30, %31, " \
    "%32, %33, %34, %35, %36, %37, %38, %39, %40, %41, %42, %43, %44, %45, %46, %47, " \
    "%48, %49, %50, %51, %52, %53, %54, %55, %56, %57, %58, %59, %60, %61, %62, %63, " \
    "%64, %65, %66, %67, %68, %69, %70, %71}"
template <int TA, int TB>
__device__ __forceinline__ void wgmma_ss_n144(float (&d)[72], uint64_t da, uint64_t db, int scale_d) {
    asm volatile(
        "{\n.reg .pred p;\nsetp.ne.b32 p, %74, 0;\n"
        "wgmma.mma_async.sync.aligned.m64n144k16.f32.bf16.bf16 " REGS72 ", %72, %73, p, 1, 1, %75, %76;\n}\n"
        : ACC72(d) : "l"(da), "l"(db), "r"(scale_d), "n"(TA), "n"(TB));
}

__device__ __forceinline__ uint32_t pack_bf16(float lo, float hi) {
    __nv_bfloat162 v = __floats2bfloat162_rn(lo, hi);
    return *reinterpret_cast<uint32_t*>(&v);
}

constexpr int K1_STAGES = 5;
constexpr int STAGE_BYTES = 34816;
constexpr int X_CHUNK_BYTES = SQ * 64 * 2;
constexpr int K1_Q_OFF = K1_STAGES * STAGE_BYTES;
constexpr int K1_BAR_OFF = K1_Q_OFF + 3 * 16384;
constexpr int K1_SMEM = K1_BAR_OFF + 256 + 1024;

struct K1Maps {
    CUtensorMap x[2], wq[2], k[2], v[2], o;
};

__global__ void __launch_bounds__(512, 1)
attn_kernel(const __grid_constant__ K1Maps maps)
{
    extern __shared__ uint8_t smem_raw[];
    uint32_t sbase = (smem_u32(smem_raw) + 1023) & ~1023u;
    const uint32_t bar_full = sbase + K1_BAR_OFF;
    const uint32_t bar_empty = bar_full + 8 * K1_STAGES;
    const int tid = threadIdx.x;
    const int wg = tid >> 7;

    if (tid == 0) {
        for (int s = 0; s < K1_STAGES; s++) {
            mbar_init(bar_full + 8 * s, 1);
            mbar_init(bar_empty + 8 * s, 12);
        }
        asm volatile("fence.mbarrier_init.release.cluster;" ::: "memory");
    }
    __syncthreads();

    if (wg == 0) {
        reg_dealloc<32>();
        if (tid == 0) {
            int stage = 0; uint32_t phase = 1;
            for (int item = blockIdx.x; item < N_ITEMS; item += gridDim.x) {
                const int blk = item >> 9;
                const int b = (item >> 5) & 15;
                const int h = item & 31;
                for (int c = 0; c < 8; c++) {
                    mbar_wait(bar_empty + 8 * stage, phase);
                    const uint32_t dst = sbase + stage * STAGE_BYTES;
                    const uint32_t fb = bar_full + 8 * stage;
                    mbar_expect_tx(fb, STAGE_BYTES);
                    tma_load_2d(dst, &maps.x[blk], fb, c * 64, b * SQ);
                    tma_load_2d(dst + X_CHUNK_BYTES, &maps.wq[blk], fb, h * DH, c * 64);
                    tma_load_2d(dst + X_CHUNK_BYTES + 8192, &maps.wq[blk], fb, h * DH + 64, c * 64);
                    if (++stage == K1_STAGES) { stage = 0; phase ^= 1; }
                }
                const int row0 = (b * NH + h) * SK;
                for (int j = 0; j < 8; j++) {
                    mbar_wait(bar_empty + 8 * stage, phase);
                    const uint32_t dst = sbase + stage * STAGE_BYTES;
                    const uint32_t fb = bar_full + 8 * stage;
                    mbar_expect_tx(fb, 32768);
                    const CUtensorMap* m = (j & 1) ? &maps.v[blk] : &maps.k[blk];
                    const int r = row0 + (j >> 1) * 128;
                    tma_load_2d(dst, m, fb, 0, r);
                    tma_load_2d(dst + 16384, m, fb, 64, r);
                    if (++stage == K1_STAGES) { stage = 0; phase ^= 1; }
                }
            }
        }
    } else {
        reg_alloc<160>();
        const int w = wg - 1;
        const int t = tid & 127;
        const int warp = t >> 5;
        const int lane = t & 31;
        const int r0 = warp * 16 + (lane >> 2);
        const int cq = (lane & 3) * 2;
        const uint32_t qbase = sbase + K1_Q_OFF + w * 16384;
        const float sl2 = 0.08838834764831845f * 1.4426950408889634f;

        int stage = 0; uint32_t phase = 0;
        for (int item = blockIdx.x; item < N_ITEMS; item += gridDim.x) {
            const int blk = item >> 9;
            const int b = (item >> 5) & 15;
            const int h = item & 31;

            float o[64];
            {
                int prev_stage = -1;
                for (int c = 0; c < 8; c++) {
                    mbar_wait(bar_full + 8 * stage, phase);
                    const uint32_t st = sbase + stage * STAGE_BYTES;
                    wgmma_fence();
#pragma unroll
                    for (int kk = 0; kk < 4; kk++) {
                        uint64_t da = make_desc(st + w * 8192 + kk * 32, 16, 1024);
                        uint64_t db = make_desc(st + X_CHUNK_BYTES + kk * 2048, 8192, 1024);
                        wgmma_ss_n128<0, 1>(o, da, db, (c | kk) != 0);
                    }
                    wgmma_commit();
                    if (prev_stage >= 0) {
                        wgmma_wait<1>();
                        if (lane == 0) mbar_arrive(bar_empty + 8 * prev_stage);
                    }
                    prev_stage = stage;
                    if (++stage == K1_STAGES) { stage = 0; phase ^= 1; }
                }
                wgmma_wait<0>();
                if (lane == 0) mbar_arrive(bar_empty + 8 * prev_stage);
                if (t == 0) bulk_wait_read0();
                named_bar_sync(1 + w, 128);
#pragma unroll
                for (int j = 0; j < 16; j++) {
                    const int blkc = j >> 3;
                    const int g = j & 7;
                    uint32_t a0 = qbase + blkc * 8192 + r0 * 128 + ((g ^ (r0 & 7)) << 4) + cq * 2;
                    uint32_t a1 = qbase + blkc * 8192 + (r0 + 8) * 128 + ((g ^ (r0 & 7)) << 4) + cq * 2;
                    uint32_t v0 = pack_bf16(o[4 * j], o[4 * j + 1]);
                    uint32_t v1 = pack_bf16(o[4 * j + 2], o[4 * j + 3]);
                    asm volatile("st.shared.b32 [%0], %1;" :: "r"(a0), "r"(v0) : "memory");
                    asm volatile("st.shared.b32 [%0], %1;" :: "r"(a1), "r"(v1) : "memory");
                }
                fence_proxy_async();
                named_bar_sync(1 + w, 128);
            }

            float m0 = -INFINITY, m1 = -INFINITY, l0 = 0.f, l1 = 0.f;
            for (int j = 0; j < 4; j++) {
                float s[64];
                mbar_wait(bar_full + 8 * stage, phase);
                {
                    const uint32_t st = sbase + stage * STAGE_BYTES;
                    wgmma_fence();
#pragma unroll
                    for (int kk = 0; kk < 8; kk++) {
                        uint64_t da = make_desc(qbase + (kk >> 2) * 8192 + (kk & 3) * 32, 16, 1024);
                        uint64_t db = make_desc(st + (kk >> 2) * 16384 + (kk & 3) * 32, 16, 1024);
                        wgmma_ss_n128<0, 0>(s, da, db, kk != 0);
                    }
                    wgmma_commit();
                    wgmma_wait<0>();
                    if (lane == 0) mbar_arrive(bar_empty + 8 * stage);
                    if (++stage == K1_STAGES) { stage = 0; phase ^= 1; }
                }
                float mx0 = m0, mx1 = m1;
#pragma unroll
                for (int i = 0; i < 16; i++) {
                    mx0 = fmaxf(mx0, fmaxf(s[4 * i], s[4 * i + 1]));
                    mx1 = fmaxf(mx1, fmaxf(s[4 * i + 2], s[4 * i + 3]));
                }
                mx0 = fmaxf(mx0, __shfl_xor_sync(0xffffffffu, mx0, 1));
                mx0 = fmaxf(mx0, __shfl_xor_sync(0xffffffffu, mx0, 2));
                mx1 = fmaxf(mx1, __shfl_xor_sync(0xffffffffu, mx1, 1));
                mx1 = fmaxf(mx1, __shfl_xor_sync(0xffffffffu, mx1, 2));
                const float a0 = exp2f((m0 - mx0) * sl2);
                const float a1 = exp2f((m1 - mx1) * sl2);
                m0 = mx0; m1 = mx1;
                const float ms0 = mx0 * sl2, ms1 = mx1 * sl2;
                float sum0 = 0.f, sum1 = 0.f;
                uint32_t p[32];
#pragma unroll
                for (int i = 0; i < 16; i++) {
                    float e0 = exp2f(fmaf(s[4 * i], sl2, -ms0));
                    float e1 = exp2f(fmaf(s[4 * i + 1], sl2, -ms0));
                    float e2 = exp2f(fmaf(s[4 * i + 2], sl2, -ms1));
                    float e3 = exp2f(fmaf(s[4 * i + 3], sl2, -ms1));
                    sum0 += e0 + e1;
                    sum1 += e2 + e3;
                    p[2 * i] = pack_bf16(e0, e1);
                    p[2 * i + 1] = pack_bf16(e2, e3);
                }
                l0 = l0 * a0 + sum0;
                l1 = l1 * a1 + sum1;
                if (j > 0) {
#pragma unroll
                    for (int i = 0; i < 16; i++) {
                        o[4 * i] *= a0; o[4 * i + 1] *= a0;
                        o[4 * i + 2] *= a1; o[4 * i + 3] *= a1;
                    }
                }
                mbar_wait(bar_full + 8 * stage, phase);
                {
                    const uint32_t st = sbase + stage * STAGE_BYTES;
                    wgmma_fence();
#pragma unroll
                    for (int kk = 0; kk < 8; kk++) {
                        uint64_t db = make_desc(st + kk * 2048, 16384, 1024);
                        wgmma_rs_n128<1>(o, p[4 * kk], p[4 * kk + 1], p[4 * kk + 2], p[4 * kk + 3], db, (j | kk) != 0);
                    }
                    wgmma_commit();
                    wgmma_wait<0>();
                    if (lane == 0) mbar_arrive(bar_empty + 8 * stage);
                    if (++stage == K1_STAGES) { stage = 0; phase ^= 1; }
                }
            }
            l0 += __shfl_xor_sync(0xffffffffu, l0, 1);
            l0 += __shfl_xor_sync(0xffffffffu, l0, 2);
            l1 += __shfl_xor_sync(0xffffffffu, l1, 1);
            l1 += __shfl_xor_sync(0xffffffffu, l1, 2);
            const float inv0 = 1.f / l0, inv1 = 1.f / l1;
#pragma unroll
            for (int j = 0; j < 16; j++) {
                const int blkc = j >> 3;
                const int g = j & 7;
                uint32_t a0 = qbase + blkc * 8192 + r0 * 128 + ((g ^ (r0 & 7)) << 4) + cq * 2;
                uint32_t a1 = qbase + blkc * 8192 + (r0 + 8) * 128 + ((g ^ (r0 & 7)) << 4) + cq * 2;
                uint32_t v0 = pack_bf16(o[4 * j] * inv0, o[4 * j + 1] * inv0);
                uint32_t v1 = pack_bf16(o[4 * j + 2] * inv1, o[4 * j + 3] * inv1);
                asm volatile("st.shared.b32 [%0], %1;" :: "r"(a0), "r"(v0) : "memory");
                asm volatile("st.shared.b32 [%0], %1;" :: "r"(a1), "r"(v1) : "memory");
            }
            fence_proxy_async();
            named_bar_sync(1 + w, 128);
            if (t == 0) {
                tma_store_3d(&maps.o, qbase, h * DH, w * 64, blk * NB + b);
                tma_store_3d(&maps.o, qbase + 8192, h * DH + 64, w * 64, blk * NB + b);
                bulk_commit();
            }
        }
        if (t == 0) bulk_wait0();
    }
}

constexpr int K2_STAGES = 6;
constexpr int K2_BAR_OFF = K2_STAGES * STAGE_BYTES;
constexpr int K2_SMEM = K2_BAR_OFF + 256 + 1024;

struct K2Maps {
    CUtensorMap wo[2], o;
};

__global__ void __launch_bounds__(384, 1)
oproj_kernel(const __grid_constant__ K2Maps maps, __nv_bfloat16* __restrict__ out)
{
    extern __shared__ uint8_t smem_raw[];
    uint32_t sbase = (smem_u32(smem_raw) + 1023) & ~1023u;
    uint8_t* sgen = smem_raw + (sbase - smem_u32(smem_raw));
    const uint32_t bar_full = sbase + K2_BAR_OFF;
    const uint32_t bar_empty = bar_full + 8 * K2_STAGES;
    const int tid = threadIdx.x;
    const int wg = tid >> 7;
    const int blk = blockIdx.x >> 6;
    const int b = (blockIdx.x >> 2) & 15;
    const int ns = blockIdx.x & 3;

    if (tid == 0) {
        for (int s = 0; s < K2_STAGES; s++) {
            mbar_init(bar_full + 8 * s, 1);
            mbar_init(bar_empty + 8 * s, 8);
        }
        asm volatile("fence.mbarrier_init.release.cluster;" ::: "memory");
    }
    __syncthreads();

    if (wg == 0) {
        if (tid == 0) {
            int stage = 0; uint32_t phase = 1;
            for (int c = 0; c < 64; c++) {
                mbar_wait(bar_empty + 8 * stage, phase);
                const uint32_t dst = sbase + stage * STAGE_BYTES;
                const uint32_t fb = bar_full + 8 * stage;
                mbar_expect_tx(fb, STAGE_BYTES);
                tma_load_3d(dst, &maps.o, fb, c * 64, 0, blk * NB + b);
                tma_load_2d(dst + X_CHUNK_BYTES, &maps.wo[blk], fb, ns * 128, c * 64);
                tma_load_2d(dst + X_CHUNK_BYTES + 8192, &maps.wo[blk], fb, ns * 128 + 64, c * 64);
                if (++stage == K2_STAGES) { stage = 0; phase ^= 1; }
            }
        }
    } else {
        const int w = wg - 1;
        const int t = tid & 127;
        const int warp = t >> 5;
        const int lane = t & 31;
        float acc[72];
        int stage = 0; uint32_t phase = 0;
        int prev_stage = -1;
        for (int c = 0; c < 64; c++) {
            mbar_wait(bar_full + 8 * stage, phase);
            const uint32_t st = sbase + stage * STAGE_BYTES;
            wgmma_fence();
#pragma unroll
            for (int kk = 0; kk < 4; kk++) {
                uint64_t da = make_desc(st + X_CHUNK_BYTES + w * 8192 + kk * 2048, 8192, 1024);
                uint64_t db = make_desc(st + kk * 32, 16, 1024);
                wgmma_ss_n144<1, 0>(acc, da, db, (c | kk) != 0);
            }
            wgmma_commit();
            if (prev_stage >= 0) {
                wgmma_wait<1>();
                if (lane == 0) mbar_arrive(bar_empty + 8 * prev_stage);
            }
            prev_stage = stage;
            if (++stage == K2_STAGES) { stage = 0; phase ^= 1; }
        }
        wgmma_wait<0>();
        named_bar_sync(1, 256);
        constexpr int PITCH = 272;
        const int m0 = w * 64 + warp * 16 + (lane >> 2);
#pragma unroll
        for (int j = 0; j < 18; j++) {
            const int n = j * 8 + (lane & 3) * 2;
            __nv_bfloat16* p0 = reinterpret_cast<__nv_bfloat16*>(sgen + n * PITCH) + m0;
            __nv_bfloat16* p1 = reinterpret_cast<__nv_bfloat16*>(sgen + (n + 1) * PITCH) + m0;
            p0[0] = __float2bfloat16(acc[4 * j]);
            p1[0] = __float2bfloat16(acc[4 * j + 1]);
            p0[8] = __float2bfloat16(acc[4 * j + 2]);
            p1[8] = __float2bfloat16(acc[4 * j + 3]);
        }
        named_bar_sync(1, 256);
        const int tt = tid - 128;
        __nv_bfloat16* obase = out + (size_t)(b * SQ) * 1024 + blk * 512 + ns * 128;
        for (int i = tt; i < SQ * 16; i += 256) {
            const int n = i >> 4, g = i & 15;
            uint4 v = *reinterpret_cast<const uint4*>(sgen + n * PITCH + g * 16);
            *reinterpret_cast<uint4*>(obase + (size_t)n * 1024 + g * 8) = v;
        }
    }
}

typedef CUresult (*EncodeFn)(CUtensorMap*, CUtensorMapDataType, cuuint32_t, void*, const cuuint64_t*,
                             const cuuint64_t*, const cuuint32_t*, const cuuint32_t*, CUtensorMapInterleave,
                             CUtensorMapSwizzle, CUtensorMapL2promotion, CUtensorMapFloatOOBfill);

static void make_map(EncodeFn fn, CUtensorMap* m, const void* ptr, int rank, const uint64_t* dims,
                     const uint32_t* box) {
    cuuint64_t gd[3]; cuuint64_t gs[2]; cuuint32_t bx[3]; cuuint32_t es[3] = {1, 1, 1};
    uint64_t stride = 2;
    for (int i = 0; i < rank; i++) {
        gd[i] = dims[i]; bx[i] = box[i];
        stride *= dims[i];
        if (i < rank - 1) gs[i] = stride;
    }
    fn(m, CU_TENSOR_MAP_DATA_TYPE_BFLOAT16, rank, const_cast<void*>(ptr), gd, gs, bx, es,
       CU_TENSOR_MAP_INTERLEAVE_NONE, CU_TENSOR_MAP_SWIZZLE_128B, CU_TENSOR_MAP_L2_PROMOTION_L2_256B,
       CU_TENSOR_MAP_FLOAT_OOB_FILL_NONE);
}

extern "C" void kernel_launch(void* const* d_in, const int* in_sizes, int n_in,
                              void* d_out, int out_size) {
    static K1Maps m1;
    static K2Maps m2;
    static bool init = false;
    if (!init) {
        void* fnp = nullptr;
        cudaDriverEntryPointQueryResult qres;
        cudaGetDriverEntryPoint("cuTensorMapEncodeTiled", &fnp, cudaEnableDefault, &qres);
        EncodeFn fn = (EncodeFn)fnp;
        void* optr = nullptr;
        cudaGetSymbolAddress(&optr, g_o);
        for (int blk = 0; blk < 2; blk++) {
            const void* x = d_in[blk * 5 + 0];
            const void* kc = d_in[blk * 5 + 1];
            const void* vc = d_in[blk * 5 + 2];
            const void* wq = d_in[blk * 5 + 3];
            const void* wo = d_in[blk * 5 + 4];
            { uint64_t d[2] = {DM, (uint64_t)NB * SQ}; uint32_t bx[2] = {64, SQ}; make_map(fn, &m1.x[blk], x, 2, d, bx); }
            { uint64_t d[2] = {HD, DM}; uint32_t bx[2] = {64, 64}; make_map(fn, &m1.wq[blk], wq, 2, d, bx); }
            { uint64_t d[2] = {DH, (uint64_t)NB * NH * SK}; uint32_t bx[2] = {64, 128}; make_map(fn, &m1.k[blk], kc, 2, d, bx); }
            { uint64_t d[2] = {DH, (uint64_t)NB * NH * SK}; uint32_t bx[2] = {64, 128}; make_map(fn, &m1.v[blk], vc, 2, d, bx); }
            { uint64_t d[2] = {DM, HD}; uint32_t bx[2] = {64, 64}; make_map(fn, &m2.wo[blk], wo, 2, d, bx); }
        }
        { uint64_t d[3] = {HD, SQ, 2 * NB}; uint32_t bx[3] = {64, 64, 1}; make_map(fn, &m1.o, optr, 3, d, bx); }
        { uint64_t d[3] = {HD, SQ, 2 * NB}; uint32_t bx[3] = {64, SQ, 1}; make_map(fn, &m2.o, optr, 3, d, bx); }
        cudaFuncSetAttribute(attn_kernel, cudaFuncAttributeMaxDynamicSharedMemorySize, K1_SMEM);
        cudaFuncSetAttribute(oproj_kernel, cudaFuncAttributeMaxDynamicSharedMemorySize, K2_SMEM);
        init = true;
    }
    attn_kernel<<<132, 512, K1_SMEM>>>(m1);
    oproj_kernel<<<128, 384, K2_SMEM>>>(m2, (__nv_bfloat16*)d_out);
}
```
